```python
import torch

def _softmax(x, axis=-1):
    return torch.softmax(x, dim=axis)
def _gelu(x):
    return torch.nn.functional.gelu(x, approximate="tanh")
def _silu(x):
    return torch.nn.functional.silu(x)
def _sigmoid(x):
    return torch.sigmoid(x)
def _layernorm(x, axis=-1, eps=1e-5):
    m = x.mean(dim=axis, keepdim=True)
    v = x.var(dim=axis, keepdim=True, unbiased=False)
    return (x - m) / torch.sqrt(v + eps)
def _scatter_add(tgt, idx, src, axis=0):
    return tgt.clone().index_add_(axis, idx, src)
def _segment_sum(src, seg, n):
    out = torch.zeros((n,) + src.shape[1:], dtype=src.dtype)
    return out.index_add_(0, seg, src)
def _pad(x, pw):
    flat = tuple(v for pair in reversed(pw) for v in pair)
    return torch.nn.functional.pad(x, flat)

kernel_name = 'parallel_sum__ssm_conv_s5__dense_activation_mish__prompt'

def setup_inputs():

    _w = (lambda a: (lambda t: t.to(torch.bfloat16) if t.is_floating_point() else t)(torch.as_tensor(a)))
    def _A_setup():
        B, S, D = 1, 2048, 512
        P = D
        Lambda_re = -0.5 * (lambda _x: torch.exp(torch.as_tensor(_x)))((lambda *s: torch.randn(*s, dtype=torch.bfloat16) * 0.2)(P))
        Lambda_im = (lambda *s: torch.randn(*s, dtype=torch.bfloat16) * 0.8)(P) * 1.0
        B_re = (lambda *s: torch.randn(*s, dtype=torch.bfloat16) * 0.2)(P, D) * (D ** -0.5)
        B_im = (lambda *s: torch.randn(*s, dtype=torch.bfloat16) * 0.2)(P, D) * (D ** -0.5)
        C_re = (lambda *s: torch.randn(*s, dtype=torch.bfloat16) * 0.2)(D, P) * (P ** -0.5)
        C_im = (lambda *s: torch.randn(*s, dtype=torch.bfloat16) * 0.2)(D, P) * (P ** -0.5)
        log_dt = (lambda *s: torch.randn(*s, dtype=torch.bfloat16) * 0.2)(P) * 0.3 - 2.0
        Dskip = (lambda *s: torch.randn(*s, dtype=torch.bfloat16) * 0.05)(D)
        return {
            "x": _w((lambda *s: torch.randn(*s, dtype=torch.bfloat16) * 0.05)(B, S, D)),
            "Lambda_re": _w(Lambda_re),
            "Lambda_im": _w(Lambda_im),
            "B_re": _w(B_re),
            "B_im": _w(B_im),
            "C_re": _w(C_re),
            "C_im": _w(C_im),
            "log_dt": _w(log_dt),
            "Dskip": _w(Dskip),
        }
    _A_in = _A_setup()

    def _B_setup():
        B, S, D, F = 1, 2048, 512, 1376
        return {
            "x": _w((lambda *s: torch.randn(*s, dtype=torch.bfloat16) * 0.05)(B, S, D)),
            "w1": _w((lambda *s: torch.randn(*s, dtype=torch.bfloat16) * 0.8)(D, F) * (D ** -0.5)),
            "b1": _w((lambda *s: torch.randn(*s, dtype=torch.bfloat16) * 0.2)(F)),
            "w2": _w((lambda *s: torch.randn(*s, dtype=torch.bfloat16) * 0.2)(F, D) * (F ** -0.5)),
        }
    _B_in = _B_setup()

    return {
        "A_x": _A_in["x"],
        "A_Lambda_re": _A_in["Lambda_re"],
        "A_Lambda_im": _A_in["Lambda_im"],
        "A_B_re": _A_in["B_re"],
        "A_B_im": _A_in["B_im"],
        "A_C_re": _A_in["C_re"],
        "A_C_im": _A_in["C_im"],
        "A_log_dt": _A_in["log_dt"],
        "A_Dskip": _A_in["Dskip"],
        "B_x": _B_in["x"],
        "B_w1": _B_in["w1"],
        "B_b1": _B_in["b1"],
        "B_w2": _B_in["w2"],
    }

def reference(A_x, A_Lambda_re, A_Lambda_im, A_B_re, A_B_im, A_C_re, A_C_im, A_log_dt, A_Dskip, B_x, B_w1, B_b1, B_w2):
    def _A_ref(x, Lambda_re, Lambda_im, B_re, B_im, C_re, C_im, log_dt, Dskip):
        Bsz, L, H = x.shape
        Lam = Lambda_re + 1j * Lambda_im
        Bmat = B_re + 1j * B_im
        Cmat = C_re + 1j * C_im
        dt = torch.exp(log_dt)
        Lam_bar = torch.exp(dt * Lam)
        B_bar = ((Lam_bar - 1.0) / Lam)[:, None] * Bmat
        Bu = torch.einsum("bld,pd->blp", x + 0j, B_bar)
        h = torch.zeros_like(Bu[:, 0, :])
        hs = []
        for t in range(L):
            h = Lam_bar[None, :] * h + Bu[:, t, :]
            hs.append(h)
        hseq = torch.stack(hs, 1)
        y = 2.0 * torch.einsum("blp,dp->bld", hseq, Cmat).real + x * Dskip[None, None, :]
        return y

    def _B_ref(x, w1, b1, w2):
        h = torch.einsum("bsd,df->bsf", x, w1) + b1
        sp = torch.log1p(torch.exp(-torch.abs(h))) + torch.where(h > 0, h, torch.zeros_like(h))
        act = h * torch.tanh(sp)
        return torch.einsum("bsf,fd->bsd", act, w2)

    x = A_x
    xn = _layernorm(x, axis=-1)
    return x + _A_ref(xn, A_Lambda_re, A_Lambda_im, A_B_re, A_B_im, A_C_re, A_C_im, A_log_dt, A_Dskip) + _B_ref(xn, B_w1, B_b1, B_w2)
```

```cpp
#include <cuda_runtime.h>
#include <cuda_bf16.h>
#include <cuda.h>
#include <stdint.h>

namespace {

constexpr int L_ = 2048, D_ = 512, P_ = 512, F_ = 1376;
constexpr int KT = 2 * P_ + F_;
constexpr int NCH = 16;
constexpr int FG = 176;

__device__ __align__(1024) __nv_bfloat16 g_xn[L_ * D_];
constexpr int KP = 2432;
__device__ __align__(1024) __nv_bfloat16 g_a2[L_ * KP];
__device__ __align__(16) unsigned long long g_agg[NCH * P_ * 2];
__device__ int g_epoch;
__device__ __align__(1024) __nv_bfloat16 g_bcopy[2 * P_ * D_];

#define TS(k, i)
#define TSB(k, i)
__device__ __forceinline__ uint32_t smem_u32(const void* p) { return (uint32_t)__cvta_generic_to_shared(p); }
__device__ __forceinline__ void mbar_init(uint32_t bar, int cnt) { asm volatile("mbarrier.init.shared::cta.b64 [%0], %1;" :: "r"(bar), "r"(cnt)); }
__device__ __forceinline__ void mbar_expect_tx(uint32_t bar, uint32_t bytes) { asm volatile("mbarrier.arrive.expect_tx.shared::cta.b64 _, [%0], %1;" :: "r"(bar), "r"(bytes) : "memory"); }
__device__ __forceinline__ void mbar_arrive(uint32_t bar) { asm volatile("mbarrier.arrive.shared::cta.b64 _, [%0];" :: "r"(bar) : "memory"); }
__device__ __forceinline__ void mbar_wait(uint32_t bar, uint32_t parity) {
    for (uint32_t it = 0; it < (1u << 20); ++it) {
        uint32_t ok;
        asm volatile("{\n.reg .pred p;\nmbarrier.try_wait.parity.shared::cta.b64 p, [%1], %2;\nselp.u32 %0, 1, 0, p;\n}\n"
                     : "=r"(ok) : "r"(bar), "r"(parity) : "memory");
        if (ok) return;
    }
}
__device__ __forceinline__ void tma_load_2d(uint32_t dst, const CUtensorMap* map, int c0, int c1, uint32_t bar) {
    asm volatile("cp.async.bulk.tensor.2d.shared::cluster.global.mbarrier::complete_tx::bytes [%0], [%1, {%3, %4}], [%2];"
                 :: "r"(dst), "l"(map), "r"(bar), "r"(c0), "r"(c1) : "memory");
}
__device__ __forceinline__ void tma_reduce_add_2d(const CUtensorMap* map, int c0, int c1, uint32_t src) {
    asm volatile("cp.reduce.async.bulk.tensor.2d.global.shared::cta.add.tile.bulk_group [%0, {%2, %3}], [%1];"
                 :: "l"(map), "r"(src), "r"(c0), "r"(c1) : "memory");
}
__device__ __forceinline__ void pdl_wait() { asm volatile("griddepcontrol.wait;" ::: "memory"); }
__device__ __forceinline__ void pdl_launch() { asm volatile("griddepcontrol.launch_dependents;" ::: "memory"); }
__device__ __forceinline__ void wg_fence() { asm volatile("wgmma.fence.sync.aligned;" ::: "memory"); }
__device__ __forceinline__ void wg_commit() { asm volatile("wgmma.commit_group.sync.aligned;" ::: "memory"); }
template <int N> __device__ __forceinline__ void wg_wait() { asm volatile("wgmma.wait_group.sync.aligned %0;" :: "n"(N) : "memory"); }
__device__ __forceinline__ void named_bar(int id, int n) { asm volatile("bar.sync %0, %1;" :: "r"(id), "r"(n) : "memory"); }
__device__ __forceinline__ void named_arrive(int id, int n) { asm volatile("bar.arrive %0, %1;" :: "r"(id), "r"(n) : "memory"); }
__device__ __forceinline__ uint64_t desc_k(uint32_t addr) {
    return (uint64_t)((addr & 0x3FFFF) >> 4) | ((uint64_t)1 << 16) | ((uint64_t)64 << 32) | ((uint64_t)1 << 62);
}
__device__ __forceinline__ uint64_t desc_mn(uint32_t addr) {
    return (uint64_t)((addr & 0x3FFFF) >> 4) | ((uint64_t)512 << 16) | ((uint64_t)64 << 32) | ((uint64_t)1 << 62);
}
__device__ __forceinline__ float bf16r(float x) { return __bfloat162float(__float2bfloat16_rn(x)); }
__device__ __forceinline__ float2 cmul(float2 a, float2 b) { return make_float2(a.x * b.x - a.y * b.y, a.x * b.y + a.y * b.x); }
__device__ __forceinline__ uint32_t pack_bf16(float a, float b) { __nv_bfloat162 p = __floats2bfloat162_rn(a, b); return *reinterpret_cast<uint32_t*>(&p); }
__device__ __forceinline__ float lo_f(uint32_t w) { return __uint_as_float(w << 16); }
__device__ __forceinline__ float hi_f(uint32_t w) { return __uint_as_float(w & 0xFFFF0000u); }

template<int N, int TB> __device__ __forceinline__ void wgmma_ss(float (&d)[N/2], uint64_t da, uint64_t db, int sc);
template<> __device__ __forceinline__ void wgmma_ss<128,0>(float (&d)[64], uint64_t da, uint64_t db, int sc) {
  asm volatile("{\n.reg .pred p;\nsetp.ne.b32 p, %66, 0;\n"
    "wgmma.mma_async.sync.aligned.m64n128k16.f32.bf16.bf16 {%0, %1, %2, %3, %4, %5, %6, %7, %8, %9, %10, %11, %12, %13, %14, %15, %16, %17, %18, %19, %20, %21, %22, %23, %24, %25, %26, %27, %28, %29, %30, %31, %32, %33, %34, %35, %36, %37, %38, %39, %40, %41, %42, %43, %44, %45, %46, %47, %48, %49, %50, %51, %52, %53, %54, %55, %56, %57, %58, %59, %60, %61, %62, %63}, %64, %65, p, 1, 1, 0, 0;\n}\n"
    : "+f"(d[0]), "+f"(d[1]), "+f"(d[2]), "+f"(d[3]), "+f"(d[4]), "+f"(d[5]), "+f"(d[6]), "+f"(d[7]), "+f"(d[8]), "+f"(d[9]), "+f"(d[10]), "+f"(d[11]), "+f"(d[12]), "+f"(d[13]), "+f"(d[14]), "+f"(d[15]), "+f"(d[16]), "+f"(d[17]), "+f"(d[18]), "+f"(d[19]), "+f"(d[20]), "+f"(d[21]), "+f"(d[22]), "+f"(d[23]), "+f"(d[24]), "+f"(d[25]), "+f"(d[26]), "+f"(d[27]), "+f"(d[28]), "+f"(d[29]), "+f"(d[30]), "+f"(d[31]), "+f"(d[32]), "+f"(d[33]), "+f"(d[34]), "+f"(d[35]), "+f"(d[36]), "+f"(d[37]), "+f"(d[38]), "+f"(d[39]), "+f"(d[40]), "+f"(d[41]), "+f"(d[42]), "+f"(d[43]), "+f"(d[44]), "+f"(d[45]), "+f"(d[46]), "+f"(d[47]), "+f"(d[48]), "+f"(d[49]), "+f"(d[50]), "+f"(d[51]), "+f"(d[52]), "+f"(d[53]), "+f"(d[54]), "+f"(d[55]), "+f"(d[56]), "+f"(d[57]), "+f"(d[58]), "+f"(d[59]), "+f"(d[60]), "+f"(d[61]), "+f"(d[62]), "+f"(d[63]) : "l"(da), "l"(db), "r"(sc));
}
template<> __device__ __forceinline__ void wgmma_ss<176,1>(float (&d)[88], uint64_t da, uint64_t db, int sc) {
  asm volatile("{\n.reg .pred p;\nsetp.ne.b32 p, %90, 0;\n"
    "wgmma.mma_async.sync.aligned.m64n176k16.f32.bf16.bf16 {%0, %1, %2, %3, %4, %5, %6, %7, %8, %9, %10, %11, %12, %13, %14, %15, %16, %17, %18, %19, %20, %21, %22, %23, %24, %25, %26, %27, %28, %29, %30, %31, %32, %33, %34, %35, %36, %37, %38, %39, %40, %41, %42, %43, %44, %45, %46, %47, %48, %49, %50, %51, %52, %53, %54, %55, %56, %57, %58, %59, %60, %61, %62, %63, %64, %65, %66, %67, %68, %69, %70, %71, %72, %73, %74, %75, %76, %77, %78, %79, %80, %81, %82, %83, %84, %85, %86, %87}, %88, %89, p, 1, 1, 0, 1;\n}\n"
    : "+f"(d[0]), "+f"(d[1]), "+f"(d[2]), "+f"(d[3]), "+f"(d[4]), "+f"(d[5]), "+f"(d[6]), "+f"(d[7]), "+f"(d[8]), "+f"(d[9]), "+f"(d[10]), "+f"(d[11]), "+f"(d[12]), "+f"(d[13]), "+f"(d[14]), "+f"(d[15]), "+f"(d[16]), "+f"(d[17]), "+f"(d[18]), "+f"(d[19]), "+f"(d[20]), "+f"(d[21]), "+f"(d[22]), "+f"(d[23]), "+f"(d[24]), "+f"(d[25]), "+f"(d[26]), "+f"(d[27]), "+f"(d[28]), "+f"(d[29]), "+f"(d[30]), "+f"(d[31]), "+f"(d[32]), "+f"(d[33]), "+f"(d[34]), "+f"(d[35]), "+f"(d[36]), "+f"(d[37]), "+f"(d[38]), "+f"(d[39]), "+f"(d[40]), "+f"(d[41]), "+f"(d[42]), "+f"(d[43]), "+f"(d[44]), "+f"(d[45]), "+f"(d[46]), "+f"(d[47]), "+f"(d[48]), "+f"(d[49]), "+f"(d[50]), "+f"(d[51]), "+f"(d[52]), "+f"(d[53]), "+f"(d[54]), "+f"(d[55]), "+f"(d[56]), "+f"(d[57]), "+f"(d[58]), "+f"(d[59]), "+f"(d[60]), "+f"(d[61]), "+f"(d[62]), "+f"(d[63]), "+f"(d[64]), "+f"(d[65]), "+f"(d[66]), "+f"(d[67]), "+f"(d[68]), "+f"(d[69]), "+f"(d[70]), "+f"(d[71]), "+f"(d[72]), "+f"(d[73]), "+f"(d[74]), "+f"(d[75]), "+f"(d[76]), "+f"(d[77]), "+f"(d[78]), "+f"(d[79]), "+f"(d[80]), "+f"(d[81]), "+f"(d[82]), "+f"(d[83]), "+f"(d[84]), "+f"(d[85]), "+f"(d[86]), "+f"(d[87]) : "l"(da), "l"(db), "r"(sc));
}
template<> __device__ __forceinline__ void wgmma_ss<128,1>(float (&d)[64], uint64_t da, uint64_t db, int sc) {
  asm volatile("{\n.reg .pred p;\nsetp.ne.b32 p, %66, 0;\n"
    "wgmma.mma_async.sync.aligned.m64n128k16.f32.bf16.bf16 {%0, %1, %2, %3, %4, %5, %6, %7, %8, %9, %10, %11, %12, %13, %14, %15, %16, %17, %18, %19, %20, %21, %22, %23, %24, %25, %26, %27, %28, %29, %30, %31, %32, %33, %34, %35, %36, %37, %38, %39, %40, %41, %42, %43, %44, %45, %46, %47, %48, %49, %50, %51, %52, %53, %54, %55, %56, %57, %58, %59, %60, %61, %62, %63}, %64, %65, p, 1, 1, 0, 1;\n}\n"
    : "+f"(d[0]), "+f"(d[1]), "+f"(d[2]), "+f"(d[3]), "+f"(d[4]), "+f"(d[5]), "+f"(d[6]), "+f"(d[7]), "+f"(d[8]), "+f"(d[9]), "+f"(d[10]), "+f"(d[11]), "+f"(d[12]), "+f"(d[13]), "+f"(d[14]), "+f"(d[15]), "+f"(d[16]), "+f"(d[17]), "+f"(d[18]), "+f"(d[19]), "+f"(d[20]), "+f"(d[21]), "+f"(d[22]), "+f"(d[23]), "+f"(d[24]), "+f"(d[25]), "+f"(d[26]), "+f"(d[27]), "+f"(d[28]), "+f"(d[29]), "+f"(d[30]), "+f"(d[31]), "+f"(d[32]), "+f"(d[33]), "+f"(d[34]), "+f"(d[35]), "+f"(d[36]), "+f"(d[37]), "+f"(d[38]), "+f"(d[39]), "+f"(d[40]), "+f"(d[41]), "+f"(d[42]), "+f"(d[43]), "+f"(d[44]), "+f"(d[45]), "+f"(d[46]), "+f"(d[47]), "+f"(d[48]), "+f"(d[49]), "+f"(d[50]), "+f"(d[51]), "+f"(d[52]), "+f"(d[53]), "+f"(d[54]), "+f"(d[55]), "+f"(d[56]), "+f"(d[57]), "+f"(d[58]), "+f"(d[59]), "+f"(d[60]), "+f"(d[61]), "+f"(d[62]), "+f"(d[63]) : "l"(da), "l"(db), "r"(sc));
}

__global__ void __launch_bounds__(256) ln_kernel(const __nv_bfloat16* __restrict__ x, const __nv_bfloat16* __restrict__ dskip,
                                                 float* __restrict__ out) {
    TS(0, 0);
    pdl_launch();
    int row = blockIdx.x * 8 + (threadIdx.x >> 5);
    int lane = threadIdx.x & 31;
    const uint4* src = reinterpret_cast<const uint4*>(x + (size_t)row * D_);
    uint4 v[2], dk[2];
    v[0] = src[lane]; v[1] = src[lane + 32];
    dk[0] = reinterpret_cast<const uint4*>(dskip)[lane]; dk[1] = reinterpret_cast<const uint4*>(dskip)[lane + 32];
    float f[16];
#pragma unroll
    for (int i = 0; i < 2; ++i) {
        const uint32_t* w = reinterpret_cast<const uint32_t*>(&v[i]);
#pragma unroll
        for (int j = 0; j < 4; ++j) { f[i * 8 + j * 2] = lo_f(w[j]); f[i * 8 + j * 2 + 1] = hi_f(w[j]); }
    }
    float s = 0.f;
#pragma unroll
    for (int i = 0; i < 16; ++i) s += f[i];
#pragma unroll
    for (int o = 16; o > 0; o >>= 1) s += __shfl_xor_sync(0xffffffffu, s, o);
    float mean = s * (1.0f / D_);
    float q = 0.f;
#pragma unroll
    for (int i = 0; i < 16; ++i) { float d = f[i] - mean; q += d * d; }
#pragma unroll
    for (int o = 16; o > 0; o >>= 1) q += __shfl_xor_sync(0xffffffffu, q, o);
    float mb = bf16r(mean);
    float vb = bf16r(q * (1.0f / D_));
    float sd = bf16r(sqrtf(bf16r(vb + 1e-5f)));
#pragma unroll
    for (int i = 0; i < 2; ++i) {
        uint4 o;
        uint32_t* w = reinterpret_cast<uint32_t*>(&o);
        const uint32_t* dw = reinterpret_cast<const uint32_t*>(&dk[i]);
        float base[8];
#pragma unroll
        for (int j = 0; j < 4; ++j) {
            float a = bf16r(f[i * 8 + j * 2] - mb) / sd;
            float b = bf16r(f[i * 8 + j * 2 + 1] - mb) / sd;
            w[j] = pack_bf16(a, b);
            base[j * 2] = f[i * 8 + j * 2] + bf16r(lo_f(w[j]) * lo_f(dw[j]));
            base[j * 2 + 1] = f[i * 8 + j * 2 + 1] + bf16r(hi_f(w[j]) * hi_f(dw[j]));
        }
        reinterpret_cast<uint4*>(g_xn + (size_t)row * D_)[lane + 32 * i] = o;
        float4* od = reinterpret_cast<float4*>(out + (size_t)row * D_ + (lane + 32 * i) * 8);
        od[0] = make_float4(base[0], base[1], base[2], base[3]);
        od[1] = make_float4(base[4], base[5], base[6], base[7]);
    }
    TS(0, 1);
}

constexpr int K1_STAGES = 4;
constexpr int K1_RING = 131072;
constexpr int K1_STAGE_BYTES = 24576;
constexpr int K1_MISC = K1_RING + K1_STAGES * K1_STAGE_BYTES;
constexpr int K1_SMEM = K1_MISC + 2048 + 1024;

__device__ __forceinline__ float ex2_approx(float x) { float y; asm("ex2.approx.ftz.f32 %0, %1;" : "=f"(y) : "f"(x)); return y; }
__device__ __forceinline__ float rcp_approx(float x) { float y; asm("rcp.approx.ftz.f32 %0, %1;" : "=f"(y) : "f"(x)); return y; }
__device__ __forceinline__ void tma_load_4d(uint32_t dst, const CUtensorMap* map, int c0, int c1, int c2, int c3, uint32_t bar) {
    asm volatile("cp.async.bulk.tensor.4d.shared::cluster.global.mbarrier::complete_tx::bytes [%0], [%1, {%3, %4, %5, %6}], [%2];"
                 :: "r"(dst), "l"(map), "r"(bar), "r"(c0), "r"(c1), "r"(c2), "r"(c3) : "memory");
}
__device__ __forceinline__ void tma_store_2d(const CUtensorMap* map, int c0, int c1, uint32_t src) {
    asm volatile("cp.async.bulk.tensor.2d.global.shared::cta.tile.bulk_group [%0, {%2, %3}], [%1];"
                 :: "l"(map), "r"(src), "r"(c0), "r"(c1) : "memory");
}
__device__ __forceinline__ float2 cfma(float2 a, float2 b, float2 c) {
    return make_float2(fmaf(a.x, b.x, fmaf(-a.y, b.y, c.x)), fmaf(a.x, b.y, fmaf(a.y, b.x, c.y)));
}

__global__ void __launch_bounds__(512, 1) k1_kernel(
    const __grid_constant__ CUtensorMap m_xn, const __grid_constant__ CUtensorMap m_bint,
    const __grid_constant__ CUtensorMap m_w1, const __grid_constant__ CUtensorMap m_sth,
    const __grid_constant__ CUtensorMap m_sta, const __grid_constant__ CUtensorMap m_st64, const int swap_ri,
    const __nv_bfloat16* __restrict__ lam_re, const __nv_bfloat16* __restrict__ lam_im,
    const __nv_bfloat16* __restrict__ log_dt, const __nv_bfloat16* __restrict__ b1,
    const __nv_bfloat16* __restrict__ c_re, const __nv_bfloat16* __restrict__ c_im, const __nv_bfloat16* __restrict__ w2) {
    extern __shared__ uint8_t smem_raw[];
    uint8_t* smem = reinterpret_cast<uint8_t*>((reinterpret_cast<uintptr_t>(smem_raw) + 1023) & ~(uintptr_t)1023);
    uint8_t* misc = smem + K1_MISC;
    float* s_b1 = reinterpret_cast<float*>(misc + 1024);
    uint64_t* bars = reinterpret_cast<uint64_t*>(misc + 1792);
    const uint32_t sbase = smem_u32(smem);
    const uint32_t bar_x = smem_u32(bars), bar_full = bar_x + 64, bar_empty = bar_x + 96, bar_go = bar_x + 128;

    const int c = blockIdx.x >> 3, g = blockIdx.x & 7;
    const int tid = threadIdx.x, warp = tid >> 5, lane = tid & 31;

    TS(1, 0);
    if (tid == 0) {
        for (int i = 0; i < 8; ++i) mbar_init(bar_x + 8 * i, 1);
        for (int s = 0; s < K1_STAGES; ++s) { mbar_init(bar_full + 8 * s, 1); mbar_init(bar_empty + 8 * s, 8); }
        mbar_init(bar_go, 8);
        asm volatile("fence.mbarrier_init.release.cluster;" ::: "memory");
    }
    __syncthreads();

    if (warp < 8) {
        const int wg = __shfl_sync(0xffffffffu, warp >> 2, 0), q = lane & 3;
        const int chl = wg * 32 + (warp & 3) * 8 + (lane >> 2);
        float2 lam, coef, l2, l4, l8, lq, l128;
        {
            const int p = g * 64 + chl;
            float a = __bfloat162float(lam_re[p]), b = __bfloat162float(lam_im[p]);
            float dt = bf16r(expf(__bfloat162float(log_dt[p])));
            float er = expf(dt * a), sn, cs;
            sincosf(dt * b, &sn, &cs);
            lam = make_float2(er * cs, er * sn);
            float nr = lam.x - 1.0f, ni = lam.y;
            float den = a * a + b * b;
            coef = make_float2(2.0f * (nr * a + ni * b) / den, 2.0f * (ni * a - nr * b) / den);
            l2 = cmul(lam, lam); l4 = cmul(l2, l2); l8 = cmul(l4, l4);
            lq = (q & 1) ? l2 : make_float2(1.f, 0.f);
            if (q & 2) lq = cmul(lq, l4);
            l128 = l8;
#pragma unroll
            for (int i = 0; i < 4; ++i) l128 = cmul(l128, l128);
        }
        const uint32_t tag = (uint32_t)(*reinterpret_cast<volatile int*>(&g_epoch)) + 1u;
        float acc_s[64];
        const uint64_t dW = desc_k(sbase + K1_RING + wg * 8192), dX = desc_k(sbase);
#pragma unroll
        for (int kb = 0; kb < 8; ++kb) {
            const int s = kb & 3;
            mbar_wait(bar_x + 8 * kb, 0);
            mbar_wait(bar_full + 8 * s, (kb >> 2) & 1);
            if (kb == 0) TS(1, 1);
            if (kb == 7 && lane == 0) mbar_arrive(bar_go);
            wg_fence();
#pragma unroll
            for (int k = 0; k < 4; ++k)
                wgmma_ss<128, 0>(acc_s, dW + ((s * K1_STAGE_BYTES + k * 32) >> 4), dX + ((kb * 16384 + k * 32) >> 4), (kb | k) != 0);
            wg_commit();
            if (kb > 0) {
                wg_wait<1>();
                if (lane == 0) mbar_arrive(bar_empty + 8 * ((kb - 1) & 3));
            }
        }
        wg_wait<0>();
        if (lane == 0) mbar_arrive(bar_empty + 8 * 3);
        named_arrive(1, 512);
        if (swap_ri) {
#pragma unroll
            for (int j = 0; j < 16; ++j) {
                float t0 = acc_s[4 * j], t1 = acc_s[4 * j + 1];
                acc_s[4 * j] = acc_s[4 * j + 2]; acc_s[4 * j + 1] = acc_s[4 * j + 3];
                acc_s[4 * j + 2] = t0; acc_s[4 * j + 3] = t1;
            }
        }
        TS(1, 2);
        const int p = g * 64 + chl;
        {
            float2 a = make_float2(0.f, 0.f);
#pragma unroll
            for (int j = 0; j < 16; ++j)
                a = cfma(l8, a, cfma(lam, make_float2(acc_s[4 * j], acc_s[4 * j + 2]), make_float2(acc_s[4 * j + 1], acc_s[4 * j + 3])));
            float2 l6q = (q & 1) ? make_float2(1.f, 0.f) : l2;
            if (!(q & 2)) l6q = cmul(l6q, l4);
            a = cmul(a, l6q);
            a.x += __shfl_xor_sync(0xffffffffu, a.x, 1); a.y += __shfl_xor_sync(0xffffffffu, a.y, 1);
            a.x += __shfl_xor_sync(0xffffffffu, a.x, 2); a.y += __shfl_xor_sync(0xffffffffu, a.y, 2);
            if (q == 0) {
                const unsigned long long t = (unsigned long long)tag << 32;
                asm volatile("st.relaxed.gpu.global.v2.b64 [%0], {%1, %2};" :: "l"(&g_agg[(size_t)(c * P_ + p) * 2]),
                             "l"(t | __float_as_uint(a.x)), "l"(t | __float_as_uint(a.y)) : "memory");
            }
        }
        TS(1, 3);
        float2 cin = make_float2(0.f, 0.f);
        {
            const float2 l256 = cmul(l128, l128), l512 = cmul(l256, l256);
            const int nq = (c - q + 3) >> 2;
            const int elast = c - 1 - (q + 4 * (nq - 1));
            float2 wgt = (elast & 1) ? l128 : make_float2(1.f, 0.f);
            if (elast & 2) wgt = cmul(wgt, l256);
#pragma unroll 1
            for (int m = nq - 1; m >= 0; --m) {
                const unsigned long long* src = &g_agg[(size_t)((q + 4 * m) * P_ + p) * 2];
                unsigned long long v0, v1;
                for (uint32_t it = 0; it < (1u << 22); ++it) {
                    asm volatile("ld.relaxed.gpu.global.v2.b64 {%0, %1}, [%2];" : "=l"(v0), "=l"(v1) : "l"(src) : "memory");
                    if ((uint32_t)(v0 >> 32) == tag && (uint32_t)(v1 >> 32) == tag) break;
                    __nanosleep(20);
                }
                cin = cfma(wgt, make_float2(__uint_as_float((uint32_t)v0), __uint_as_float((uint32_t)v1)), cin);
                wgt = cmul(wgt, l512);
            }
            __syncwarp();
            cin.x += __shfl_xor_sync(0xffffffffu, cin.x, 1); cin.y += __shfl_xor_sync(0xffffffffu, cin.y, 1);
            cin.x += __shfl_xor_sync(0xffffffffu, cin.x, 2); cin.y += __shfl_xor_sync(0xffffffffu, cin.y, 2);
        }
        TS(1, 4);
        uint32_t hpk[32];
#pragma unroll
        for (int jb = 0; jb < 4; ++jb) {
            float2 ex[4], tot[4];
#pragma unroll
            for (int jj = 0; jj < 4; ++jj) {
                const int j = jb * 4 + jj;
                float2 w0 = make_float2(acc_s[4 * j], acc_s[4 * j + 2]), w1 = make_float2(acc_s[4 * j + 1], acc_s[4 * j + 3]);
                float2 a = cfma(lam, w0, w1);
                float2 t;
                t.x = __shfl_up_sync(0xffffffffu, a.x, 1, 4); t.y = __shfl_up_sync(0xffffffffu, a.y, 1, 4);
                if (q >= 1) a = cfma(l2, t, a);
                t.x = __shfl_up_sync(0xffffffffu, a.x, 2, 4); t.y = __shfl_up_sync(0xffffffffu, a.y, 2, 4);
                if (q >= 2) a = cfma(l4, t, a);
                t.x = __shfl_up_sync(0xffffffffu, a.x, 1, 4); t.y = __shfl_up_sync(0xffffffffu, a.y, 1, 4);
                ex[jj] = (q >= 1) ? t : make_float2(0.f, 0.f);
                tot[jj].x = __shfl_sync(0xffffffffu, a.x, 3, 4); tot[jj].y = __shfl_sync(0xffffffffu, a.y, 3, 4);
            }
#pragma unroll
            for (int jj = 0; jj < 4; ++jj) {
                const int j = jb * 4 + jj;
                float2 E = cfma(lq, cin, ex[jj]);
                float2 h0 = cfma(lam, E, make_float2(acc_s[4 * j], acc_s[4 * j + 2]));
                float2 h1 = cfma(lam, h0, make_float2(acc_s[4 * j + 1], acc_s[4 * j + 3]));
                cin = cfma(l8, cin, tot[jj]);
                float2 o0 = cmul(coef, h0), o1 = cmul(coef, h1);
                hpk[2 * j] = pack_bf16(o0.x, o1.x);
                hpk[2 * j + 1] = pack_bf16(-o0.y, -o1.y);
            }
        }
        TS(1, 5);
        named_bar(7, 512);
        {
            const int chunk = wg * 4 + (warp & 3), mi = lane >> 3, ti = lane & 7;
            const uint32_t hst = sbase + 49152 + (mi & 1) * 16384 + ((mi >> 1) * 8 + ti) * 128 + ((chunk ^ ti) << 4);
#pragma unroll
            for (int j = 0; j < 16; j += 2)
                asm volatile("stmatrix.sync.aligned.m8n8.x4.trans.shared.b16 [%0], {%1, %2, %3, %4};"
                             :: "r"(hst + j * 1024), "r"(hpk[2 * j]), "r"(hpk[2 * j + 1]), "r"(hpk[2 * j + 2]), "r"(hpk[2 * j + 3]) : "memory");
            asm volatile("fence.proxy.async.shared::cta;" ::: "memory");
            named_bar(2, 256);
            if (tid == 0) {
                tma_store_2d(&m_sth, g * 64, c * 128, sbase + 49152);
                tma_store_2d(&m_sth, P_ + g * 64, c * 128, sbase + 49152 + 16384);
                asm volatile("cp.async.bulk.commit_group;" ::: "memory");
                asm volatile("cp.async.bulk.wait_group 0;" ::: "memory");
            }
        }
        TS(1, 7);
    } else {
        const int wg = __shfl_sync(0xffffffffu, (warp >> 2) - 2, 0), q = lane & 3;
        {
            const int t = tid - 256;
            if (t < FG) { int n = g * FG + t; reinterpret_cast<__nv_bfloat16*>(s_b1)[t] = (n < F_) ? b1[n] : __float2bfloat16_rn(0.f); }
        }
        float acc_f[88];
        const uint64_t dXa = desc_k(sbase + wg * 8192), dW1 = desc_mn(sbase + K1_RING);
        const bool producer = (tid == 256);
        if (tid == 288) {
            asm volatile("cp.async.bulk.prefetch.L2.global [%0], %1;" :: "l"(reinterpret_cast<const char*>(c_re) + blockIdx.x * 4096), "r"(4096) : "memory");
            asm volatile("cp.async.bulk.prefetch.L2.global [%0], %1;" :: "l"(reinterpret_cast<const char*>(c_im) + blockIdx.x * 4096), "r"(4096) : "memory");
            asm volatile("cp.async.bulk.prefetch.L2.global [%0], %1;" :: "l"(reinterpret_cast<const char*>(w2) + blockIdx.x * 11008), "r"(11008) : "memory");
        }
        auto load_w1 = [&](int i) {
            const int s = i & 3;
            mbar_wait(bar_empty + 8 * s, ((i >> 2) & 1) ^ 1);
            const uint32_t st = sbase + K1_RING + s * K1_STAGE_BYTES, fb = bar_full + 8 * s;
            mbar_expect_tx(fb, 24576);
#pragma unroll
            for (int b = 0; b < 3; ++b) tma_load_2d(st + b * 8192, &m_w1, g * FG + b * 64, (i - 8) * 64, fb);
        };
        if (producer) {
            for (int i = 0; i < 4; ++i) {
                mbar_expect_tx(bar_full + 8 * i, 16384);
                tma_load_4d(sbase + K1_RING + i * K1_STAGE_BYTES, &m_bint, i * 64, 0, 0, g * 8, bar_full + 8 * i);
            }
            pdl_wait();
            for (int kb = 0; kb < 8; ++kb) {
                mbar_expect_tx(bar_x + 8 * kb, 16384);
                tma_load_2d(sbase + kb * 16384, &m_xn, kb * 64, c * 128, bar_x + 8 * kb);
            }
            for (int i = 4; i < 8; ++i) {
                mbar_wait(bar_empty + 8 * (i & 3), 0);
                mbar_expect_tx(bar_full + 8 * (i & 3), 16384);
                tma_load_4d(sbase + K1_RING + (i & 3) * K1_STAGE_BYTES, &m_bint, i * 64, 0, 0, g * 8, bar_full + 8 * (i & 3));
            }
            for (int i = 8; i < 12; ++i) load_w1(i);
        }
        __syncwarp();
        mbar_wait(bar_go, 0);
        TSB(1, 11);
#pragma unroll
        for (int kb = 0; kb < 8; ++kb) {
            const int s = kb & 3;
            mbar_wait(bar_full + 8 * s, (kb >> 2) & 1);
            wg_fence();
#pragma unroll
            for (int k = 0; k < 4; ++k)
                wgmma_ss<176, 1>(acc_f, dXa + ((kb * 16384 + k * 32) >> 4), dW1 + ((s * K1_STAGE_BYTES + k * 2048) >> 4), (kb | k) != 0);
            wg_commit();
            if (kb > 0 && kb <= 4) {
                wg_wait<1>();
                if (lane == 0) mbar_arrive(bar_empty + 8 * ((kb - 1) & 3));
                if (producer) load_w1(11 + kb);
                __syncwarp();
            }
        }
        wg_wait<0>();
        TSB(1, 12);
        named_arrive(7, 512);
        named_bar(1, 512);
        const uint32_t sb1 = smem_u32(s_b1) + q * 4;
        const int srow = wg * 64 + (warp & 3) * 16 + ((lane >> 3) & 1) * 8 + (lane & 7), sjj = lane >> 4;
#pragma unroll
        for (int jb = 0; jb < 11; ++jb) {
            uint32_t pk[4];
            float h[8], d[8];
#pragma unroll
            for (int jj = 0; jj < 2; ++jj) {
                uint32_t bw;
                asm("ld.shared.b32 %0, [%1];" : "=r"(bw) : "r"(sb1 + (jb * 2 + jj) * 16));
#pragma unroll
                for (int hh = 0; hh < 2; ++hh) {
                    const int i = (jb * 2 + jj) * 4 + hh * 2;
                    uint32_t w = pack_bf16(acc_f[i], acc_f[i + 1]);
                    asm("add.rn.bf16x2 %0, %1, %2;" : "=r"(w) : "r"(w), "r"(bw));
                    h[jj * 4 + hh * 2] = lo_f(w); h[jj * 4 + hh * 2 + 1] = hi_f(w);
                }
            }
#pragma unroll
            for (int i = 0; i < 8; ++i) {
                float u = ex2_approx(fminf(h[i] * 1.4426950408889634f, 28.f)) + 1.0f;
                d[i] = fmaf(u, u, 1.0f);
            }
#pragma unroll
            for (int i = 0; i < 4; ++i) {
                float r = -2.0f * rcp_approx(d[2 * i] * d[2 * i + 1]);
                pk[i] = pack_bf16(h[2 * i] * fmaf(d[2 * i + 1], r, 1.0f), h[2 * i + 1] * fmaf(d[2 * i], r, 1.0f));
            }
            {
                const int j = jb * 2 + sjj;
                uint32_t ad;
                if (jb < 8) ad = sbase + (jb >> 2) * 16384 + srow * 128 + (((j & 7) ^ (srow & 7)) << 4);
                else ad = sbase + 32768 + srow * 96 + (j - 16) * 16;
                asm volatile("stmatrix.sync.aligned.m8n8.x4.shared.b16 [%0], {%1, %2, %3, %4};"
                             :: "r"(ad), "r"(pk[0]), "r"(pk[1]), "r"(pk[2]), "r"(pk[3]) : "memory");
            }
            if (jb == 3 || jb == 7 || jb == 10) {
                asm volatile("fence.proxy.async.shared::cta;" ::: "memory");
                named_bar(8 + wg, 128);
                if ((tid & 127) == 0) {
                    if (jb == 10) tma_store_2d(&m_sta, 2 * P_ + g * FG + 128, c * 128 + wg * 64, sbase + 32768 + wg * 6144);
                    else tma_store_2d(&m_st64, 2 * P_ + g * FG + (jb >> 2) * 64, c * 128 + wg * 64, sbase + (jb >> 2) * 16384 + wg * 8192);
                    asm volatile("cp.async.bulk.commit_group;" ::: "memory");
                }
            }
        }
        TSB(1, 13);
        if ((tid & 127) == 0) {
            asm volatile("cp.async.bulk.wait_group 0;" ::: "memory");
        }
    }
}

constexpr int K3_STAGES = 7;
constexpr int K3_STAGE_BYTES = 32768;
constexpr int K3_OUT = 0;
constexpr int K3_SMEM = K3_STAGES * K3_STAGE_BYTES + K3_OUT + 1024 + 1024;

template <int KS>
__device__ __forceinline__ void k3_mainloop(float (&acc)[64], uint64_t dA, uint64_t dBk, uint64_t dBm, uint32_t bar_full,
                                            uint32_t bar_empty, int lane) {
#pragma unroll
    for (int i = 0; i < 19; ++i) {
        const int s = i % K3_STAGES;
        mbar_wait(bar_full + 8 * s, (i / K3_STAGES) & 1);
        if (i == 0) TS(2, 1);
        wg_fence();
#pragma unroll
        for (int k = 0; k < 4; ++k) {
            if (KS == 0 && i < 16) wgmma_ss<128, 0>(acc, dA + ((s * K3_STAGE_BYTES + k * 32) >> 4), dBk + ((s * K3_STAGE_BYTES + k * 32) >> 4), (i | k) != 0);
            else wgmma_ss<128, 1>(acc, dA + ((s * K3_STAGE_BYTES + k * 32) >> 4), dBm + ((s * K3_STAGE_BYTES + k * 2048) >> 4), (i | k) != 0);
        }
        wg_commit();
        if (i > 0 && i <= 19 - K3_STAGES) {
            wg_wait<1>();
            if (lane == 0) mbar_arrive(bar_empty + 8 * ((i - 1) % K3_STAGES));
        }
    }
}

__global__ void __launch_bounds__(288, 1) k3_kernel(
    const __grid_constant__ CUtensorMap m_a2, const __grid_constant__ CUtensorMap m_cre,
    const __grid_constant__ CUtensorMap m_cim, const __grid_constant__ CUtensorMap m_w2,
    const __grid_constant__ CUtensorMap m_out) {
    extern __shared__ uint8_t smem_raw[];
    uint8_t* smem = reinterpret_cast<uint8_t*>((reinterpret_cast<uintptr_t>(smem_raw) + 1023) & ~(uintptr_t)1023);
    uint8_t* obuf = smem;
    uint64_t* bars = reinterpret_cast<uint64_t*>(smem + K3_STAGES * K3_STAGE_BYTES + K3_OUT);
    const uint32_t sbase = smem_u32(smem);
    const uint32_t bar_full = smem_u32(bars), bar_empty = bar_full + 8 * K3_STAGES;
    const int ks = blockIdx.x & 1, nt = (blockIdx.x >> 1) & 3, mt = blockIdx.x >> 3;
    const int tid = threadIdx.x, warp = tid >> 5, lane = tid & 31;
    const int kb0 = ks * 19, nkb = 19;

    TS(2, 0);
    if (tid == 256) {
        asm volatile("prefetch.tensormap [%0];" :: "l"(&m_a2) : "memory");
        asm volatile("prefetch.tensormap [%0];" :: "l"(ks ? &m_w2 : &m_cre) : "memory");
        asm volatile("prefetch.tensormap [%0];" :: "l"(&m_out) : "memory");
    }
    if (tid == 0) {
        for (int s = 0; s < K3_STAGES; ++s) { mbar_init(bar_full + 8 * s, 1); mbar_init(bar_empty + 8 * s, 8); }
        asm volatile("fence.mbarrier_init.release.cluster;" ::: "memory");
    }
    __syncthreads();

    if (warp == 8) {
        if (lane == 0) {
            for (int i = 0; i < nkb; ++i) {
                int kb = kb0 + i;
                int s = i % K3_STAGES;
                uint32_t ph = (i / K3_STAGES) & 1;
                mbar_wait(bar_empty + 8 * s, ph ^ 1);
                uint32_t st = sbase + s * K3_STAGE_BYTES, fb = bar_full + 8 * s;
                mbar_expect_tx(fb, K3_STAGE_BYTES);
                if (kb < 8) tma_load_2d(st + 16384, &m_cre, kb * 64, nt * 128, fb);
                else if (kb < 16) tma_load_2d(st + 16384, &m_cim, (kb - 8) * 64, nt * 128, fb);
                else {
                    tma_load_2d(st + 16384, &m_w2, nt * 128, (kb - 16) * 64, fb);
                    tma_load_2d(st + 24576, &m_w2, nt * 128 + 64, (kb - 16) * 64, fb);
                }
                if (i == 0) {
                    pdl_wait();
                    if (blockIdx.x == 0) g_epoch = g_epoch + 1;
                }
                tma_load_2d(st, &m_a2, kb * 64, mt * 128, fb);
            }
        }
    } else {
        const int wg = __shfl_sync(0xffffffffu, warp >> 2, 0);
        float acc[64];
        const uint64_t dA = desc_k(sbase + wg * 8192), dBk = desc_k(sbase + 16384), dBm = desc_mn(sbase + 16384);
        if (ks == 0) k3_mainloop<0>(acc, dA, dBk, dBm, bar_full, bar_empty, lane);
        else k3_mainloop<1>(acc, dA, dBk, dBm, bar_full, bar_empty, lane);
        wg_wait<0>();
        TS(2, 2);
        named_bar(3, 256);
        uint8_t* ob = obuf + wg * 32768;
        {
            int r0 = (warp & 3) * 16 + (lane >> 2);
#pragma unroll
            for (int j = 0; j < 16; ++j) {
                int col = j * 8 + (lane & 3) * 2;
                int box = col >> 5, cc = col & 31;
                int chunk = cc >> 2, within = (cc & 3) * 4;
#pragma unroll
                for (int h = 0; h < 2; ++h) {
                    int r = r0 + h * 8;
                    *reinterpret_cast<float2*>(ob + box * 8192 + r * 128 + ((chunk ^ (r & 7)) << 4) + within) =
                        make_float2(acc[j * 4 + h * 2], acc[j * 4 + h * 2 + 1]);
                }
            }
        }
        asm volatile("fence.proxy.async.shared::cta;" ::: "memory");
        named_bar(1 + wg, 128);
        if ((tid & 127) == 0) {
#pragma unroll
            for (int bb = 0; bb < 4; ++bb) {
                const int b = ks ? (bb ^ 2) : bb;
                tma_reduce_add_2d(&m_out, nt * 128 + b * 32, mt * 128 + wg * 64, smem_u32(ob) + b * 8192);
            }
            asm volatile("cp.async.bulk.commit_group;" ::: "memory");
            asm volatile("cp.async.bulk.wait_group 0;" ::: "memory");
        }
        TS(2, 4);
    }
}

typedef CUresult (*EncodeFn)(CUtensorMap*, CUtensorMapDataType, cuuint32_t, void*, const cuuint64_t*, const cuuint64_t*,
                             const cuuint32_t*, const cuuint32_t*, CUtensorMapInterleave, CUtensorMapSwizzle,
                             CUtensorMapL2promotion, CUtensorMapFloatOOBfill);

void make_map(EncodeFn fn, CUtensorMap* m, const void* ptr, uint64_t inner, uint64_t outer, uint32_t box_inner, uint32_t box_outer,
              bool f32 = false, bool swz = true, uint64_t pitch = 0) {
    cuuint64_t dims[2] = {inner, outer};
    cuuint64_t strides[1] = {(pitch ? pitch : inner) * (f32 ? 4 : 2)};
    cuuint32_t box[2] = {box_inner, box_outer};
    cuuint32_t es[2] = {1, 1};
    fn(m, f32 ? CU_TENSOR_MAP_DATA_TYPE_FLOAT32 : CU_TENSOR_MAP_DATA_TYPE_BFLOAT16, 2, const_cast<void*>(ptr), dims, strides, box, es,
       CU_TENSOR_MAP_INTERLEAVE_NONE, swz ? CU_TENSOR_MAP_SWIZZLE_128B : CU_TENSOR_MAP_SWIZZLE_NONE, CU_TENSOR_MAP_L2_PROMOTION_L2_256B,
       CU_TENSOR_MAP_FLOAT_OOB_FILL_NONE);
}

}

extern "C" void kernel_launch(void* const* d_in, const int* in_sizes, int n_in, void* d_out, int out_size) {
    const __nv_bfloat16* x = (const __nv_bfloat16*)d_in[0];
    const __nv_bfloat16* lam_re = (const __nv_bfloat16*)d_in[1];
    const __nv_bfloat16* lam_im = (const __nv_bfloat16*)d_in[2];
    const __nv_bfloat16* b_re = (const __nv_bfloat16*)d_in[3];
    const __nv_bfloat16* b_im = (const __nv_bfloat16*)d_in[4];
    const __nv_bfloat16* c_re = (const __nv_bfloat16*)d_in[5];
    const __nv_bfloat16* c_im = (const __nv_bfloat16*)d_in[6];
    const __nv_bfloat16* log_dt = (const __nv_bfloat16*)d_in[7];
    const __nv_bfloat16* dskip = (const __nv_bfloat16*)d_in[8];
    const __nv_bfloat16* w1 = (const __nv_bfloat16*)d_in[10];
    const __nv_bfloat16* b1 = (const __nv_bfloat16*)d_in[11];
    const __nv_bfloat16* w2 = (const __nv_bfloat16*)d_in[12];
    float* out = (float*)d_out;

    static EncodeFn enc = nullptr;
    static void *p_xn = nullptr, *p_a2 = nullptr;
    if (!enc) {
        void* fp = nullptr;
        cudaDriverEntryPointQueryResult qr;
        cudaGetDriverEntryPoint("cuTensorMapEncodeTiled", &fp, cudaEnableDefault, &qr);
        enc = (EncodeFn)fp;
        cudaGetSymbolAddress(&p_xn, g_xn);
        cudaGetSymbolAddress(&p_a2, g_a2);
        cudaFuncSetAttribute(k1_kernel, cudaFuncAttributeMaxDynamicSharedMemorySize, K1_SMEM);
        cudaFuncSetAttribute(k3_kernel, cudaFuncAttributeMaxDynamicSharedMemorySize, K3_SMEM);
    }
    CUtensorMap m_xn, m_bre, m_bim, m_w1, m_a2, m_cre, m_cim, m_w2, m_out, m_sth, m_sta;
    make_map(enc, &m_xn, p_xn, D_, L_, 64, 128);
    int swap_ri = b_im < b_re;
    {
        const char* lo = (const char*)(swap_ri ? b_im : b_re);
        const char* hi = (const char*)(swap_ri ? b_re : b_im);
        cuuint64_t dims[4] = {(cuuint64_t)D_, 8, 2, 64};
        cuuint64_t strides[3] = {(cuuint64_t)D_ * 2, (cuuint64_t)(hi - lo), (cuuint64_t)D_ * 16};
        cuuint32_t box[4] = {64, 8, 2, 8};
        cuuint32_t es[4] = {1, 1, 1, 1};
        bool ok = (strides[1] % 16 == 0) && strides[1] < (1ull << 40) && strides[1] >= (cuuint64_t)P_ * D_ * 2;
        if (ok)
            ok = enc(&m_bre, CU_TENSOR_MAP_DATA_TYPE_BFLOAT16, 4, const_cast<char*>(lo), dims, strides, box, es,
                     CU_TENSOR_MAP_INTERLEAVE_NONE, CU_TENSOR_MAP_SWIZZLE_128B, CU_TENSOR_MAP_L2_PROMOTION_L2_256B,
                     CU_TENSOR_MAP_FLOAT_OOB_FILL_NONE) == CUDA_SUCCESS;
        if (!ok) {
            void* pb = nullptr;
            cudaGetSymbolAddress(&pb, g_bcopy);
            cudaMemcpyAsync(pb, b_re, (size_t)P_ * D_ * 2, cudaMemcpyDeviceToDevice, cudaStreamPerThread);
            cudaMemcpyAsync((char*)pb + (size_t)P_ * D_ * 2, b_im, (size_t)P_ * D_ * 2, cudaMemcpyDeviceToDevice, cudaStreamPerThread);
            swap_ri = 0;
            strides[1] = (cuuint64_t)P_ * D_ * 2;
            enc(&m_bre, CU_TENSOR_MAP_DATA_TYPE_BFLOAT16, 4, pb, dims, strides, box, es,
                CU_TENSOR_MAP_INTERLEAVE_NONE, CU_TENSOR_MAP_SWIZZLE_128B, CU_TENSOR_MAP_L2_PROMOTION_L2_256B,
                CU_TENSOR_MAP_FLOAT_OOB_FILL_NONE);
        }
    }
    make_map(enc, &m_w1, w1, F_, D_, 64, 64);
    make_map(enc, &m_sth, p_a2, KT, L_, 64, 128, false, true, KP);
    make_map(enc, &m_sta, p_a2, KT, L_, 48, 64, false, false, KP);
    make_map(enc, &m_bim, p_a2, KT, L_, 64, 64, false, true, KP);
    make_map(enc, &m_a2, p_a2, KT, L_, 64, 128, false, true, KP);
    make_map(enc, &m_cre, c_re, P_, D_, 64, 128);
    make_map(enc, &m_cim, c_im, P_, D_, 64, 128);
    make_map(enc, &m_w2, w2, D_, F_, 64, 64);
    make_map(enc, &m_out, out, D_, L_, 32, 64, true);

    ln_kernel<<<L_ / 8, 256>>>(x, dskip, out);
    cudaLaunchAttribute at[1];
    at[0].id = cudaLaunchAttributeProgrammaticStreamSerialization;
    at[0].val.programmaticStreamSerializationAllowed = 1;
    cudaLaunchConfig_t cfg = {};
    cfg.gridDim = dim3(128); cfg.blockDim = dim3(512); cfg.dynamicSmemBytes = K1_SMEM; cfg.stream = cudaStreamPerThread;
    cfg.attrs = at; cfg.numAttrs = 1;
    cudaLaunchKernelEx(&cfg, k1_kernel, m_xn, m_bre, m_w1, m_sth, m_sta, m_bim, swap_ri, lam_re, lam_im, log_dt, b1, c_re, c_im, w2);
    cfg.blockDim = dim3(288); cfg.dynamicSmemBytes = K3_SMEM;
    cudaLaunchKernelEx(&cfg, k3_kernel, m_a2, m_cre, m_cim, m_w2, m_out);
}
```
